```python
import torch

def _softmax(x, axis=-1):
    return torch.softmax(x, dim=axis)

def _gelu(x):
    return torch.nn.functional.gelu(x, approximate='tanh')

def _silu(x):
    return torch.nn.functional.silu(x)

def _sigmoid(x):
    return torch.sigmoid(x)

def _layernorm(x, axis=-1, eps=1e-05):
    m = x.mean(dim=axis, keepdim=True)
    v = x.var(dim=axis, keepdim=True, unbiased=False)
    return (x - m) / torch.sqrt(v + eps)

def _scatter_add(tgt, idx, src, axis=0):
    return tgt.clone().index_add_(axis, idx, src)

def _segment_sum(src, seg, n):
    out = torch.zeros((n,) + src.shape[1:], dtype=src.dtype)
    return out.index_add_(0, seg, src)

def _pad(x, pw):
    flat = tuple((v for pair in reversed(pw) for v in pair))
    return torch.nn.functional.pad(x, flat)
kernel_name = 'adaLN_cond__gqa_block_cached__glu_gated_bilinear__decode'

def setup_inputs():

    _w = lambda a: (lambda t: t.to(torch.bfloat16) if t.is_floating_point() else t)(torch.as_tensor(a))

    def _A_setup():
        B, Sq, D = (1, 1, 512)
        Hq, Hkv, Sk, Dh = (32, 32, 4096, 128)
        assert Hq % Hkv == 0, (Hq, Hkv)
        return {'x': _w((lambda *s: torch.randn(*s, dtype=torch.bfloat16) * 0.05)(B, Sq, D)), 'k_cache': _w((lambda *s: torch.randn(*s, dtype=torch.bfloat16) * 0.8)(B, Hkv, Sk, Dh)), 'v_cache': _w((lambda *s: torch.randn(*s, dtype=torch.bfloat16) * 3.2)(B, Hkv, Sk, Dh)), 'wq': _w((lambda *s: torch.randn(*s, dtype=torch.bfloat16) * 0.8)(D, Hq * Dh) * D ** (-0.5)), 'wo': _w((lambda *s: torch.randn(*s, dtype=torch.bfloat16) * 3.2)(Hq * Dh, D) * (Hq * Dh) ** (-0.5))}
    _A_in = _A_setup()

    def _B_setup():
        B, S, D, F = (1, 1, 512, 1376)
        return {'x': _w((lambda *s: torch.randn(*s, dtype=torch.bfloat16) * 0.05)(B, S, D)), 'w_gate': _w((lambda *s: torch.randn(*s, dtype=torch.bfloat16) * 3.2)(D, F) * D ** (-0.5)), 'w_up': _w((lambda *s: torch.randn(*s, dtype=torch.bfloat16) * 3.2)(D, F) * D ** (-0.5)), 'w_down': _w((lambda *s: torch.randn(*s, dtype=torch.bfloat16) * 3.2)(F, D) * F ** (-0.5))}
    _B_in = _B_setup()
    return {'A_x': _A_in['x'], 'A_k_cache': _A_in['k_cache'], 'A_v_cache': _A_in['v_cache'], 'A_wq': _A_in['wq'], 'A_wo': _A_in['wo'], 'B_x': _B_in['x'], 'B_w_gate': _B_in['w_gate'], 'B_w_up': _B_in['w_up'], 'B_w_down': _B_in['w_down'], 'c': _w((lambda *s: torch.randn(*s, dtype=torch.bfloat16) * 0.4)(1, 512) * 8.0), 'w_mod': _w((lambda *s: torch.randn(*s, dtype=torch.bfloat16) * 0.4)(512, 6 * 512) * 512 ** (-0.5) * 8.0)}

def reference(A_x, A_k_cache, A_v_cache, A_wq, A_wo, B_x, B_w_gate, B_w_up, B_w_down, c, w_mod):

    def _A_ref(x, k_cache, v_cache, wq, wo):
        B, Sq, D = x.shape
        Hq, Dh = (32, 128)
        Hkv = k_cache.shape[1]
        rep = Hq // Hkv
        q = (lambda x, *d: x.permute(*d))((x @ wq).reshape(B, Sq, Hq, Dh), 0, 2, 1, 3)
        k = (lambda x, n, axis: torch.repeat_interleave(x, n, dim=axis))(k_cache, rep, axis=1)
        v = (lambda x, n, axis: torch.repeat_interleave(x, n, dim=axis))(v_cache, rep, axis=1)
        scores = torch.einsum('bhqd,bhkd->bhqk', q, k) * Dh ** (-0.5)
        p = _softmax(scores, axis=-1)
        o = torch.einsum('bhqk,bhkd->bhqd', p, v)
        return (lambda x, *d: x.permute(*d))(o, 0, 2, 1, 3).reshape(B, Sq, Hq * Dh) @ wo

    def _B_ref(x, w_gate, w_up, w_down):
        g = torch.einsum('bsd,df->bsf', x, w_gate)
        u = torch.einsum('bsd,df->bsf', x, w_up)
        h = g * u
        return torch.einsum('bsf,fd->bsd', h, w_down)
    x = A_x
    mod = (_silu(c) @ w_mod).reshape(c.shape[0], 6, 1, -1)
    sa, ca, ga, sb, cb, gb = (mod[:, 0].clone(), mod[:, 1].clone(), mod[:, 2].clone(), mod[:, 3].clone(), mod[:, 4].clone(), mod[:, 5].clone())
    h = _layernorm(x, axis=-1) * (1 + ca) + sa
    x = x + ga * _A_ref(h, A_k_cache, A_v_cache, A_wq, A_wo)
    h = _layernorm(x, axis=-1) * (1 + cb) + sb
    x = x + gb * _B_ref(h, B_w_gate, B_w_up, B_w_down)
    return x
```

```cpp
#include <cuda_runtime.h>
#include <cuda_bf16.h>
#include <cuda.h>
#include <stdint.h>

namespace {

constexpr int kD = 512;
constexpr int kF = 1376;
constexpr int kNCTA = 128;
constexpr int kNFFN = 86;
constexpr int kStage = 16384;
constexpr int kRing = 13;
constexpr int kWin = 4;
constexpr int kWoPos = 10;
constexpr int kThreads = 288;
constexpr unsigned kSpinMax = 1u << 24;

constexpr int E_WQ = 0;
constexpr int E_K = 2;
constexpr int E_V0 = 18;
constexpr int E_WO = E_V0 + kWoPos;
constexpr int E_V1 = E_WO + 2;
constexpr int E_FFN = E_V0 + 18;
constexpr int E_END = E_FFN + 3;

constexpr int SM_RING = 0;
constexpr int SM_P = kRing * kStage;
constexpr int SM_RED = SM_P + 8192;
constexpr int SM_RED2 = SM_RED + 1024;
constexpr int SM_X1 = SM_RED2 + 1024;
constexpr int SM_STAT = SM_X1 + 2048;
constexpr int SM_BAR = SM_STAT + 128;
constexpr int SM_TOTAL = SM_BAR + 2 * kRing * 8;
constexpr int SM_ALLOC = SM_TOTAL + 1024;

struct Maps {
    CUtensorMap wq, v, wo, wg, wu, wd;
};

__device__ unsigned int g_epoch;
__device__ __align__(128) unsigned long long g_mod[1536];
__device__ __align__(128) unsigned long long g_q[32 * 64];
__device__ __align__(128) unsigned long long g_sc[32 * 2048];
__device__ __align__(128) float4 g_accB[192];
__device__ __align__(128) float4 g_accC[192];
#define TS(i) do { } while (0)
#define TSP(i) do { } while (0)

__device__ __forceinline__ uint32_t smem_u32(const void* p) { return (uint32_t)__cvta_generic_to_shared(p); }
__device__ __forceinline__ void mbar_init(uint32_t bar, int cnt) {
    asm volatile("mbarrier.init.shared::cta.b64 [%0], %1;" ::"r"(bar), "r"(cnt) : "memory");
}
__device__ __forceinline__ void mbar_expect_tx(uint32_t bar, uint32_t bytes) {
    asm volatile("mbarrier.arrive.expect_tx.shared::cta.b64 _, [%0], %1;" ::"r"(bar), "r"(bytes) : "memory");
}
__device__ __forceinline__ void mbar_arrive(uint32_t bar) {
    asm volatile("mbarrier.arrive.shared::cta.b64 _, [%0];" ::"r"(bar) : "memory");
}
__device__ __forceinline__ void mbar_wait(uint32_t bar, uint32_t parity) {
    uint32_t ok;
    unsigned spins = 0;
    do {
        asm volatile(
            "{\n.reg .pred p;\n"
            "mbarrier.try_wait.parity.shared::cta.b64 p, [%1], %2;\n"
            "selp.u32 %0, 1, 0, p;\n}"
            : "=r"(ok) : "r"(bar), "r"(parity) : "memory");
        if (++spins > kSpinMax) __trap();
    } while (!ok);
}
__device__ __forceinline__ void bulk_load(uint32_t dst, const void* src, uint32_t bytes, uint32_t bar) {
    asm volatile("cp.async.bulk.shared::cluster.global.mbarrier::complete_tx::bytes [%0], [%1], %2, [%3];"
                 ::"r"(dst), "l"(src), "r"(bytes), "r"(bar) : "memory");
}
__device__ __forceinline__ void tma2d(uint32_t dst, const CUtensorMap* m, int c0, int c1, uint32_t bar) {
    asm volatile("cp.async.bulk.tensor.2d.shared::cluster.global.mbarrier::complete_tx::bytes [%0], [%1, {%3, %4}], [%2];"
                 ::"r"(dst), "l"(m), "r"(bar), "r"(c0), "r"(c1) : "memory");
}
__device__ __forceinline__ void tma3d(uint32_t dst, const CUtensorMap* m, int c0, int c1, int c2, uint32_t bar) {
    asm volatile("cp.async.bulk.tensor.3d.shared::cluster.global.mbarrier::complete_tx::bytes [%0], [%1, {%3, %4, %5}], [%2];"
                 ::"r"(dst), "l"(m), "r"(bar), "r"(c0), "r"(c1), "r"(c2) : "memory");
}
__device__ __forceinline__ void ldsm4t(uint32_t (&r)[4], uint32_t addr) {
    asm volatile("ldmatrix.sync.aligned.m8n8.x4.trans.shared.b16 {%0,%1,%2,%3}, [%4];"
                 : "=r"(r[0]), "=r"(r[1]), "=r"(r[2]), "=r"(r[3]) : "r"(addr) : "memory");
}
__device__ __forceinline__ uint4 lds128(uint32_t addr) {
    uint4 v;
    asm volatile("ld.shared.v4.u32 {%0,%1,%2,%3}, [%4];" : "=r"(v.x), "=r"(v.y), "=r"(v.z), "=r"(v.w) : "r"(addr) : "memory");
    return v;
}
__device__ __forceinline__ void mma16816(float (&c)[4], uint32_t a0, uint32_t a1, uint32_t a2, uint32_t a3,
                                         uint32_t b0, uint32_t b1) {
    asm volatile("mma.sync.aligned.m16n8k16.row.col.f32.bf16.bf16.f32 {%0,%1,%2,%3}, {%4,%5,%6,%7}, {%8,%9}, {%0,%1,%2,%3};"
                 : "+f"(c[0]), "+f"(c[1]), "+f"(c[2]), "+f"(c[3])
                 : "r"(a0), "r"(a1), "r"(a2), "r"(a3), "r"(b0), "r"(b1));
}
__device__ __forceinline__ void bar_consumers() { asm volatile("bar.sync 1, 256;" ::: "memory"); }

__device__ __forceinline__ float bf_lo(uint32_t v) { return __uint_as_float(v << 16); }
__device__ __forceinline__ float bf_hi(uint32_t v) { return __uint_as_float(v & 0xffff0000u); }
__device__ __forceinline__ float rbf(float x) { return __bfloat162float(__float2bfloat16_rn(x)); }
__device__ __forceinline__ uint32_t pack_bf(float lo, float hi) {
    uint32_t r;
    asm("cvt.rn.bf16x2.f32 %0, %1, %2;" : "=r"(r) : "f"(hi), "f"(lo));
    return r;
}

__device__ __forceinline__ void ll_store(unsigned long long* p, uint32_t data, uint32_t flag) {
    unsigned long long v = ((unsigned long long)flag << 32) | data;
    asm volatile("st.relaxed.gpu.global.b64 [%0], %1;" ::"l"(p), "l"(v) : "memory");
}
__device__ __forceinline__ bool ll_try2(const unsigned long long* p, uint32_t flag, uint32_t& d0, uint32_t& d1) {
    unsigned long long a, b;
    asm volatile("ld.relaxed.gpu.global.v2.b64 {%0,%1}, [%2];" : "=l"(a), "=l"(b) : "l"(p) : "memory");
    d0 = (uint32_t)a;
    d1 = (uint32_t)b;
    return (uint32_t)(a >> 32) == flag && (uint32_t)(b >> 32) == flag;
}
__device__ __forceinline__ bool ll_try1(const unsigned long long* p, uint32_t flag, uint32_t& d0) {
    unsigned long long a;
    asm volatile("ld.relaxed.gpu.global.b64 %0, [%1];" : "=l"(a) : "l"(p) : "memory");
    d0 = (uint32_t)a;
    return (uint32_t)(a >> 32) == flag;
}
__device__ __forceinline__ int perm_pair(int pair) {
    int grp = pair >> 4, pi = pair & 15;
    return grp * 16 + (pi & 3) * 4 + (pi >> 2);
}

__device__ __forceinline__ void ln_stats(const float (&v)[16], float shift, float& mean_b, float& den_b) {
    float s = 0.f, ss = 0.f;
#pragma unroll
    for (int i = 0; i < 16; i++) {
        float d = v[i] - shift;
        s += d;
        ss = fmaf(d, d, ss);
    }
#pragma unroll
    for (int o = 16; o >= 1; o >>= 1) {
        s += __shfl_xor_sync(0xffffffffu, s, o);
        ss += __shfl_xor_sync(0xffffffffu, ss, o);
    }
    float md = s * (1.f / kD);
    float var = fmaxf(ss * (1.f / kD) - md * md, 0.f);
    mean_b = rbf(shift + md);
    den_b = rbf(sqrtf(rbf(rbf(var) + 1e-5f)));
}
__device__ __forceinline__ float modulate(float x, float mean_b, float den_b, float cs, float sh) {
    float n = rbf(__fdiv_rn(rbf(x - mean_b), den_b));
    return rbf(n * rbf(1.f + cs)) + sh;
}

__global__ void __launch_bounds__(kThreads, 1)
fused_kernel(const __grid_constant__ Maps maps, const __nv_bfloat16* __restrict__ x,
             const __nv_bfloat16* __restrict__ kc, const __nv_bfloat16* __restrict__ cvec,
             const __nv_bfloat16* __restrict__ wmod, __nv_bfloat16* __restrict__ out) {
    extern __shared__ uint8_t smem_raw[];
    const uint32_t sbase = (smem_u32(smem_raw) + 1023u) & ~1023u;
    uint8_t* sptr = smem_raw + (sbase - smem_u32(smem_raw));
    const int tid = threadIdx.x, warp = tid >> 5, lane = tid & 31;
    const int b = blockIdx.x, h = b >> 2, r = b & 3;
    const uint32_t bar_full = sbase + SM_BAR, bar_empty = bar_full + kRing * 8;
    const bool is_ffn = b < kNFFN;

    if (warp == 8) {
        if (lane == 0) {
            TSP(12);
#pragma unroll 1
            for (int i = 0; i < kRing; i++) {
                mbar_init(bar_full + i * 8, 1);
                mbar_init(bar_empty + i * 8, 8);
            }
            asm volatile("fence.mbarrier_init.release.cluster;" ::: "memory");
            asm volatile("fence.proxy.async.shared::cta;" ::: "memory");
        }
        __syncwarp();
        asm volatile("bar.arrive 2, 288;" ::: "memory");
        if (lane == 0) {
            const int n_ent = is_ffn ? E_END : E_FFN;
            const char* kbase = (const char*)kc + (size_t)b * 262144;
            int s = 0, ph = 0;
            int sw = 0, phw = 0;
#pragma unroll 1
            for (int e = 0; e < n_ent; e++) {
                if (e >= kWin) {
                    mbar_wait(bar_full + sw * 8, phw);
                    if (++sw == kRing) { sw = 0; phw ^= 1; }
                }
                if (e >= kRing) mbar_wait(bar_empty + s * 8, ph ^ 1);
                const uint32_t dst = sbase + SM_RING + s * kStage, bar = bar_full + s * 8;
                mbar_expect_tx(bar, kStage);
                if (e < E_K) {
                    tma2d(dst, &maps.wq, b * 32, e * 256, bar);
                } else if (e < E_V0) {
                    bulk_load(dst, kbase + (e - E_K) * kStage, kStage, bar);
                } else if (e < E_WO) {
                    tma2d(dst, &maps.v, r * 32, h * 4096 + (e - E_V0) * 256, bar);
                } else if (e < E_V1) {
                    tma3d(dst, &maps.wo, 0, b * 32, (e - E_WO) * 4, bar);
                } else if (e < E_FFN) {
                    tma2d(dst, &maps.v, r * 32, h * 4096 + (e - E_V0 - 2) * 256, bar);
                } else if (e < E_FFN + 2) {
                    const CUtensorMap* m = (e == E_FFN) ? &maps.wg : &maps.wu;
                    tma2d(dst, m, b * 16, 0, bar);
                    tma2d(dst + 8192, m, b * 16, 256, bar);
                } else {
                    tma3d(dst, &maps.wd, 0, b * 16, 0, bar);
                }
                if (e == 0) TSP(13);
                if (++s == kRing) { s = 0; ph ^= 1; }
            }
            TSP(14);
        }
        return;
    }

    TS(0);
    const int g = lane >> 2, t = lane & 3;
    float* red = (float*)(sptr + SM_RED);
    float* red2 = (float*)(sptr + SM_RED2);
    float* x1s = (float*)(sptr + SM_X1);
    float* stat = (float*)(sptr + SM_STAT);

    uint4 wm[8];
    {
        const char* p = (const char*)wmod + (size_t)(warp * 64 + g) * 6144 + b * 48 + min(t, 2) * 16;
#pragma unroll
        for (int i = 0; i < 8; i++) wm[i] = __ldg((const uint4*)(p + (size_t)i * 8 * 6144));
    }
    uint32_t c2 = __ldg((const uint32_t*)cvec + warp * 32 + lane);
    uint32_t flag;
    asm volatile("ld.relaxed.gpu.global.u32 %0, [%1];" : "=r"(flag) : "l"(&g_epoch) : "memory");
    uint4 xa = __ldg((const uint4*)x + lane * 2), xb = __ldg((const uint4*)x + lane * 2 + 1);
    uint32_t xq[8];
#pragma unroll
    for (int i = 0; i < 8; i++)
        xq[i] = __ldg((const uint32_t*)x + (i >> 2) * 128 + warp * 16 + ((i >> 1) & 1) * 8 + (i & 1) * 4 + t);
    if (b == 0 && tid < 192) {
        g_accB[tid] = make_float4(0.f, 0.f, 0.f, 0.f);
        g_accC[tid] = make_float4(0.f, 0.f, 0.f, 0.f);
    }
    flag += 1;
    float mean1, den1;
    {
        float v[16] = {bf_lo(xa.x), bf_hi(xa.x), bf_lo(xa.y), bf_hi(xa.y), bf_lo(xa.z), bf_hi(xa.z), bf_lo(xa.w), bf_hi(xa.w),
                       bf_lo(xb.x), bf_hi(xb.x), bf_lo(xb.y), bf_hi(xb.y), bf_lo(xb.z), bf_hi(xb.z), bf_lo(xb.w), bf_hi(xb.w)};
        float shift = __shfl_sync(0xffffffffu, v[0], 0);
        ln_stats(v, shift, mean1, den1);
    }
    {
        float c0 = bf_lo(c2), c1 = bf_hi(c2);
        float s0 = rbf(__fdiv_rn(c0, 1.f + __expf(-c0))), s1 = rbf(__fdiv_rn(c1, 1.f + __expf(-c1)));
        float acc[8];
#pragma unroll
        for (int j = 0; j < 8; j++) acc[j] = 0.f;
#pragma unroll
        for (int i = 0; i < 8; i++) {
            float sa_ = __shfl_sync(0xffffffffu, s0, 4 * i + (g >> 1));
            float sb_ = __shfl_sync(0xffffffffu, s1, 4 * i + (g >> 1));
            float s = (g & 1) ? sb_ : sa_;
            acc[0] = fmaf(s, bf_lo(wm[i].x), acc[0]);
            acc[1] = fmaf(s, bf_hi(wm[i].x), acc[1]);
            acc[2] = fmaf(s, bf_lo(wm[i].y), acc[2]);
            acc[3] = fmaf(s, bf_hi(wm[i].y), acc[3]);
            acc[4] = fmaf(s, bf_lo(wm[i].z), acc[4]);
            acc[5] = fmaf(s, bf_hi(wm[i].z), acc[5]);
            acc[6] = fmaf(s, bf_lo(wm[i].w), acc[6]);
            acc[7] = fmaf(s, bf_hi(wm[i].w), acc[7]);
        }
#pragma unroll
        for (int s = 4; s >= 1; s >>= 1) {
            bool up = (g & s) != 0;
#pragma unroll
            for (int i = 0; i < s; i++) {
                float send = up ? acc[i] : acc[i + s];
                float keep = up ? acc[i + s] : acc[i];
                acc[i] = keep + __shfl_xor_sync(0xffffffffu, send, s * 4);
            }
        }
        red[warp * 32 + t * 8 + g] = acc[0];
    }
    asm volatile("bar.sync 2, 288;" ::: "memory");
    if (warp == 0) {
        float s = 0.f;
#pragma unroll
        for (int w = 0; w < 8; w++) s += red[w * 32 + lane];
        float o = __shfl_down_sync(0xffffffffu, s, 1);
        if (b == 0) __threadfence();
        if (lane < 24 && !(lane & 1)) ll_store(&g_mod[perm_pair(b * 12 + (lane >> 1))], pack_bf(s, o), flag);
    }
    TS(1);

    uint32_t hb[8];
    {
        uint32_t sa[8], ca[8];
        unsigned spins = 0;
        bool ok;
        do {
            ok = true;
#pragma unroll
            for (int i = 0; i < 4; i++) {
                int idx = ((i >> 1) * 8 + warp) * 16 + t * 4 + (i & 1) * 2;
                ok &= ll_try2(&g_mod[idx], flag, sa[2 * i], sa[2 * i + 1]);
                ok &= ll_try2(&g_mod[256 + idx], flag, ca[2 * i], ca[2 * i + 1]);
            }
            if (++spins > kSpinMax) __trap();
        } while (!ok);
        __threadfence();
#pragma unroll
        for (int i = 0; i < 8; i++) {
            float lo = modulate(bf_lo(xq[i]), mean1, den1, bf_lo(ca[i]), bf_lo(sa[i]));
            float hi = modulate(bf_hi(xq[i]), mean1, den1, bf_hi(ca[i]), bf_hi(sa[i]));
            hb[i] = pack_bf(lo, hi);
        }
    }
    TS(2);
    uint32_t vt_off[2];
    {
        int row = warp * 32 + (lane & 7) + ((lane >> 4) << 3);
        int c = (lane >> 3) & 1;
        int sw = (row >> 1) & 3;
        vt_off[0] = row * 64 + ((c ^ sw) << 4);
        vt_off[1] = row * 64 + (((c + 2) ^ sw) << 4);
    }
    int st = 0, ph = 0;
    float oacc[2][4];
#pragma unroll
    for (int m = 0; m < 2; m++)
#pragma unroll
        for (int i = 0; i < 4; i++) oacc[m][i] = 0.f;
#pragma unroll
    for (int e = 0; e < 2; e++) {
        mbar_wait(bar_full + st * 8, ph);
        uint32_t base = sbase + SM_RING + st * kStage;
        uint32_t a[4][4];
        ldsm4t(a[0], base + vt_off[0]);
        ldsm4t(a[1], base + vt_off[1]);
        ldsm4t(a[2], base + vt_off[0] + 1024);
        ldsm4t(a[3], base + vt_off[1] + 1024);
        mma16816(oacc[0], a[0][0], a[0][1], a[0][2], a[0][3], hb[e * 4 + 0], hb[e * 4 + 1]);
        mma16816(oacc[1], a[1][0], a[1][1], a[1][2], a[1][3], hb[e * 4 + 0], hb[e * 4 + 1]);
        mma16816(oacc[0], a[2][0], a[2][1], a[2][2], a[2][3], hb[e * 4 + 2], hb[e * 4 + 3]);
        mma16816(oacc[1], a[3][0], a[3][1], a[3][2], a[3][3], hb[e * 4 + 2], hb[e * 4 + 3]);
        __syncwarp();
        if (lane == 0) mbar_arrive(bar_empty + st * 8);
        if (++st == kRing) { st = 0; ph ^= 1; }
    }
    if (t == 0) {
        red2[warp * 32 + g] = oacc[0][0];
        red2[warp * 32 + g + 8] = oacc[0][2];
        red2[warp * 32 + g + 16] = oacc[1][0];
        red2[warp * 32 + g + 24] = oacc[1][2];
    }
    bar_consumers();
    if (warp == 0) {
        float s = 0.f;
#pragma unroll
        for (int w = 0; w < 8; w++) s += red2[w * 32 + lane];
        float o = __shfl_down_sync(0xffffffffu, s, 1);
        if (!(lane & 1)) ll_store(&g_q[b * 16 + (lane >> 1)], pack_bf(s, o), flag);
    }
    TS(3);
    uint32_t q[4][4];
    {
        unsigned spins = 0;
        bool ok;
        do {
            ok = true;
#pragma unroll
            for (int i = 0; i < 4; i++) {
                const unsigned long long* p = &g_q[h * 64 + (t + 4 * i) * 4];
                ok &= ll_try2(p, flag, q[i][0], q[i][1]);
                ok &= ll_try2(p + 2, flag, q[i][2], q[i][3]);
            }
            if (++spins > kSpinMax) __trap();
        } while (!ok);
    }
    TS(4);

    {
        const uint32_t koff0 = (warp * 8 + g) * 256 + ((t + 4 * (g & 1)) << 4);
        const uint32_t koff1 = (warp * 8 + g) * 256 + ((t + 4 * ((g & 1) ^ 1)) << 4);
        unsigned long long* scp = &g_sc[b * 512 + warp * 4 + t];
#pragma unroll 1
        for (int j = 0; j < 16; j++) {
            mbar_wait(bar_full + st * 8, ph);
            uint32_t base = sbase + SM_RING + st * kStage;
            uint4 k0 = lds128(base + koff0), k1 = lds128(base + koff1);
            uint4 k2 = lds128(base + koff0 + 128), k3 = lds128(base + koff1 + 128);
            float c0[4] = {0.f, 0.f, 0.f, 0.f}, c1[4] = {0.f, 0.f, 0.f, 0.f};
            mma16816(c0, q[0][0], q[1][0], q[0][1], q[1][1], k0.x, k0.y);
            mma16816(c1, q[0][2], q[1][2], q[0][3], q[1][3], k0.z, k0.w);
            mma16816(c0, q[1][0], q[0][0], q[1][1], q[0][1], k1.x, k1.y);
            mma16816(c1, q[1][2], q[0][2], q[1][3], q[0][3], k1.z, k1.w);
            mma16816(c0, q[2][0], q[3][0], q[2][1], q[3][1], k2.x, k2.y);
            mma16816(c1, q[2][2], q[3][2], q[2][3], q[3][3], k2.z, k2.w);
            mma16816(c0, q[3][0], q[2][0], q[3][1], q[2][1], k3.x, k3.y);
            mma16816(c1, q[3][2], q[2][2], q[3][3], q[2][3], k3.z, k3.w);
            __syncwarp();
            if (lane == 0) mbar_arrive(bar_empty + st * 8);
            if (++st == kRing) { st = 0; ph ^= 1; }
            const float scale = 0.08838834764831845f;
            float s0 = rbf(c0[0] + c1[0]) * scale, s1 = rbf(c0[3] + c1[3]) * scale;
            if (g == 0) ll_store(scp + j * 32, pack_bf(s0, s1), flag);
        }
    }
    TS(5);

    {
        uint32_t sv[8];
        unsigned spins = 0;
        bool ok;
        do {
            ok = true;
#pragma unroll
            for (int i = 0; i < 4; i++) ok &= ll_try2(&g_sc[h * 2048 + (tid + 256 * i) * 2], flag, sv[2 * i], sv[2 * i + 1]);
            if (++spins > kSpinMax) __trap();
        } while (!ok);
        TS(6);
        float e[16];
#pragma unroll
        for (int i = 0; i < 8; i++) { e[2 * i] = bf_lo(sv[i]); e[2 * i + 1] = bf_hi(sv[i]); }
        float m = e[0];
#pragma unroll
        for (int i = 1; i < 16; i++) m = fmaxf(m, e[i]);
#pragma unroll
        for (int o = 16; o >= 1; o >>= 1) m = fmaxf(m, __shfl_xor_sync(0xffffffffu, m, o));
        if (lane == 0) stat[warp] = m;
        bar_consumers();
#pragma unroll
        for (int w = 0; w < 8; w++) m = fmaxf(m, stat[w]);
        float sum = 0.f;
#pragma unroll
        for (int i = 0; i < 16; i++) { e[i] = __expf(e[i] - m); sum += e[i]; }
#pragma unroll
        for (int o = 16; o >= 1; o >>= 1) sum += __shfl_xor_sync(0xffffffffu, sum, o);
        if (lane == 0) stat[8 + warp] = sum;
        bar_consumers();
        sum = 0.f;
#pragma unroll
        for (int w = 0; w < 8; w++) sum += stat[8 + w];
        float inv = __frcp_rn(sum);
        uint32_t* ps = (uint32_t*)(sptr + SM_P);
#pragma unroll
        for (int i = 0; i < 8; i++) {
            int pair = (tid + 256 * (i >> 1)) * 2 + (i & 1);
            ps[perm_pair(pair)] = pack_bf(e[2 * i] * inv, e[2 * i + 1] * inv);
        }
        bar_consumers();
    }
    TS(7);

    float xo[3], gao[3], gbo[3];
    uint32_t cb[8], sb[8];
    if (is_ffn) {
        unsigned spins = 0;
        bool ok;
        uint32_t ga_[3], gb_[3];
        int col[3];
#pragma unroll
        for (int i = 0; i < 3; i++) {
            int j = min(3 * t + i, 7);
            col[i] = 64 * warp + 16 * (j >> 1) + 8 * (j & 1) + g;
            xo[i] = __bfloat162float(x[col[i]]);
        }
        do {
            ok = true;
#pragma unroll
            for (int i = 0; i < 3; i++) {
                ok &= ll_try1(&g_mod[512 + perm_pair(col[i] >> 1)], flag, ga_[i]);
                ok &= ll_try1(&g_mod[1280 + perm_pair(col[i] >> 1)], flag, gb_[i]);
            }
#pragma unroll
            for (int i = 0; i < 4; i++) {
                int idx = (warp * 2 + (i >> 1)) * 16 + t * 4 + (i & 1) * 2;
                ok &= ll_try2(&g_mod[768 + idx], flag, sb[2 * i], sb[2 * i + 1]);
                ok &= ll_try2(&g_mod[1024 + idx], flag, cb[2 * i], cb[2 * i + 1]);
            }
            if (++spins > kSpinMax) __trap();
        } while (!ok);
#pragma unroll
        for (int i = 0; i < 3; i++) {
            gao[i] = (g & 1) ? bf_hi(ga_[i]) : bf_lo(ga_[i]);
            gbo[i] = (g & 1) ? bf_hi(gb_[i]) : bf_lo(gb_[i]);
        }
    }

    uint32_t wo[4][2][4];
    const int wrow = (lane & 7) + ((lane >> 4) << 3);
    const int wc = (lane >> 3) & 1;
#pragma unroll
    for (int m = 0; m < 2; m++)
#pragma unroll
        for (int i = 0; i < 4; i++) oacc[m][i] = 0.f;
    {
        const uint32_t paddr = sbase + SM_P + warp * 64 + t * 16;
#pragma unroll 1
        for (int j = 0; j < 16; j++) {
            if (j == kWoPos) {
                int st2 = st + (warp >> 2), ph2 = ph;
                if (st2 >= kRing) { st2 -= kRing; ph2 ^= 1; }
                mbar_wait(bar_full + st2 * 8, ph2);
                uint32_t base = sbase + SM_RING + st2 * kStage + (warp & 3) * 4096;
#pragma unroll
                for (int m = 0; m < 4; m++)
#pragma unroll
                    for (int ks = 0; ks < 2; ks++)
                        ldsm4t(wo[m][ks], base + (ks * 16 + wrow) * 128 + (((2 * m + wc) ^ (wrow & 7)) << 4));
                uint32_t dep = wo[0][0][0] | wo[1][0][0] | wo[2][0][0] | wo[3][0][0] | wo[0][1][0] | wo[1][1][0] | wo[2][1][0] | wo[3][1][0];
                asm volatile("" ::"r"(dep) : "memory");
                __syncwarp();
                if (lane == 0) {
                    mbar_arrive(bar_empty + st * 8);
                    mbar_arrive(bar_empty + ((st + 1 == kRing) ? 0 : st + 1) * 8);
                }
                st += 2;
                if (st >= kRing) { st -= kRing; ph ^= 1; }
            }
            uint4 pb = lds128(paddr + j * 512);
            mbar_wait(bar_full + st * 8, ph);
            uint32_t base = sbase + SM_RING + st * kStage;
            uint32_t a[4][4];
            ldsm4t(a[0], base + vt_off[0]);
            ldsm4t(a[1], base + vt_off[1]);
            ldsm4t(a[2], base + vt_off[0] + 1024);
            ldsm4t(a[3], base + vt_off[1] + 1024);
            mma16816(oacc[0], a[0][0], a[0][1], a[0][2], a[0][3], pb.x, pb.y);
            mma16816(oacc[1], a[1][0], a[1][1], a[1][2], a[1][3], pb.x, pb.y);
            mma16816(oacc[0], a[2][0], a[2][1], a[2][2], a[2][3], pb.z, pb.w);
            mma16816(oacc[1], a[3][0], a[3][1], a[3][2], a[3][3], pb.z, pb.w);
            __syncwarp();
            if (lane == 0) mbar_arrive(bar_empty + st * 8);
            if (++st == kRing) { st = 0; ph ^= 1; }
        }
    }
    TS(8);
    if (t == 0) {
        red[(g) * 8 + warp] = oacc[0][0];
        red[(g + 8) * 8 + warp] = oacc[0][2];
        red[(g + 16) * 8 + warp] = oacc[1][0];
        red[(g + 24) * 8 + warp] = oacc[1][2];
    }
    bar_consumers();
    const int vidx = warp * 24 + g * 3 + t;
    {
        float4 p0 = *(const float4*)&red[lane * 8], p1 = *(const float4*)&red[lane * 8 + 4];
        float s = ((p0.x + p0.y) + (p0.z + p0.w)) + ((p1.x + p1.y) + (p1.z + p1.w));
        float o = __shfl_down_sync(0xffffffffu, s, 1);
        uint32_t pk = pack_bf(s, o);
        uint32_t b0 = __shfl_sync(0xffffffffu, pk, 2 * t), b1 = __shfl_sync(0xffffffffu, pk, 2 * t + 8);
        uint32_t b2 = __shfl_sync(0xffffffffu, pk, 2 * t + 16), b3 = __shfl_sync(0xffffffffu, pk, 2 * t + 24);
        float y[4][4];
#pragma unroll
        for (int m = 0; m < 4; m++) {
#pragma unroll
            for (int i = 0; i < 4; i++) y[m][i] = 0.f;
            mma16816(y[m], wo[m][0][0], wo[m][0][1], wo[m][0][2], wo[m][0][3], b0, b1);
        }
#pragma unroll
        for (int m = 0; m < 4; m++) mma16816(y[m], wo[m][1][0], wo[m][1][1], wo[m][1][2], wo[m][1][3], b2, b3);
        float v0 = t == 0 ? y[0][0] : (t == 1 ? y[1][2] : y[3][0]);
        float v1 = t == 0 ? y[0][2] : (t == 1 ? y[2][0] : y[3][2]);
        float v2 = t == 0 ? y[1][0] : (t == 1 ? y[2][2] : 0.f);
        if (t < 3)
            asm volatile("red.relaxed.gpu.global.add.v4.f32 [%0], {%1,%2,%3,%4};"
                         ::"l"(&g_accB[vidx]), "f"(v0), "f"(v1), "f"(v2), "f"(1.0f) : "memory");
    }
    TS(9);
    if (!is_ffn) return;

    uint32_t wg[4][4], wu[4][4], wd[4][4];
    {
        const int row = warp * 64 + wrow;
        const uint32_t off = row * 32 + ((wc ^ ((row >> 2) & 1)) << 4);
        mbar_wait(bar_full + st * 8, ph);
        uint32_t base = sbase + SM_RING + st * kStage;
#pragma unroll
        for (int ks = 0; ks < 4; ks++) ldsm4t(wg[ks], base + off + ks * 512);
        if (++st == kRing) { st = 0; ph ^= 1; }
        mbar_wait(bar_full + st * 8, ph);
        base = sbase + SM_RING + st * kStage;
#pragma unroll
        for (int ks = 0; ks < 4; ks++) ldsm4t(wu[ks], base + off + ks * 512);
        if (++st == kRing) { st = 0; ph ^= 1; }
        mbar_wait(bar_full + st * 8, ph);
        base = sbase + SM_RING + st * kStage + warp * 2048;
#pragma unroll
        for (int m = 0; m < 4; m++) ldsm4t(wd[m], base + wrow * 128 + (((2 * m + wc) ^ (wrow & 7)) << 4));
    }
    TS(10);
    float x1o[3];
    {
        float4 a;
        unsigned spins = 0;
        if (t < 3) {
            do {
                asm volatile("ld.relaxed.gpu.global.v4.f32 {%0,%1,%2,%3}, [%4];"
                             : "=f"(a.x), "=f"(a.y), "=f"(a.z), "=f"(a.w) : "l"(&g_accB[vidx]) : "memory");
                if (++spins > kSpinMax) __trap();
            } while (a.w != (float)kNCTA);
            x1o[0] = rbf(xo[0] + rbf(gao[0] * rbf(a.x)));
            x1o[1] = rbf(xo[1] + rbf(gao[1] * rbf(a.y)));
            x1o[2] = rbf(xo[2] + rbf(gao[2] * rbf(a.z)));
#pragma unroll
            for (int i = 0; i < 3; i++) {
                int j = 3 * t + i;
                if (j < 8) x1s[64 * warp + 16 * (j >> 1) + 8 * (j & 1) + g] = x1o[i];
            }
        }
    }
    bar_consumers();
    TS(11);
    if (b == 0 && tid == 0) g_epoch = flag;
    {
        float v[16];
#pragma unroll
        for (int i = 0; i < 4; i++) {
            float4 f = *(const float4*)&x1s[i * 128 + lane * 4];
            v[4 * i] = f.x; v[4 * i + 1] = f.y; v[4 * i + 2] = f.z; v[4 * i + 3] = f.w;
        }
        float2 xr[8];
#pragma unroll
        for (int i = 0; i < 8; i++) xr[i] = *(const float2*)&x1s[warp * 64 + (i >> 1) * 16 + (i & 1) * 8 + 2 * t];
        float mean2, den2;
        ln_stats(v, x1s[0], mean2, den2);
        float gacc[4] = {0.f, 0.f, 0.f, 0.f}, uacc[4] = {0.f, 0.f, 0.f, 0.f};
#pragma unroll
        for (int ks = 0; ks < 4; ks++) {
            uint32_t hh[2];
#pragma unroll
            for (int i = 0; i < 2; i++) {
                int k = ks * 2 + i;
                float lo = modulate(xr[k].x, mean2, den2, bf_lo(cb[k]), bf_lo(sb[k]));
                float hi = modulate(xr[k].y, mean2, den2, bf_hi(cb[k]), bf_hi(sb[k]));
                hh[i] = pack_bf(lo, hi);
            }
            mma16816(gacc, wg[ks][0], wg[ks][1], wg[ks][2], wg[ks][3], hh[0], hh[1]);
            mma16816(uacc, wu[ks][0], wu[ks][1], wu[ks][2], wu[ks][3], hh[0], hh[1]);
        }
        if (t == 0) {
            red2[(g) * 8 + warp] = gacc[0];
            red2[(g + 8) * 8 + warp] = gacc[2];
            red2[(g + 16) * 8 + warp] = uacc[0];
            red2[(g + 24) * 8 + warp] = uacc[2];
        }
    }
    bar_consumers();
    {
        float4 p0 = *(const float4*)&red2[lane * 8], p1 = *(const float4*)&red2[lane * 8 + 4];
        float s = rbf(((p0.x + p0.y) + (p0.z + p0.w)) + ((p1.x + p1.y) + (p1.z + p1.w)));
        float hv = s * __shfl_down_sync(0xffffffffu, s, 16);
        float o = __shfl_down_sync(0xffffffffu, hv, 1);
        uint32_t pk = pack_bf(hv, o);
        uint32_t b0 = __shfl_sync(0xffffffffu, pk, 2 * t), b1 = __shfl_sync(0xffffffffu, pk, 2 * t + 8);
        float y[4][4];
#pragma unroll
        for (int m = 0; m < 4; m++) {
#pragma unroll
            for (int i = 0; i < 4; i++) y[m][i] = 0.f;
            mma16816(y[m], wd[m][0], wd[m][1], wd[m][2], wd[m][3], b0, b1);
        }
        float v0 = t == 0 ? y[0][0] : (t == 1 ? y[1][2] : y[3][0]);
        float v1 = t == 0 ? y[0][2] : (t == 1 ? y[2][0] : y[3][2]);
        float v2 = t == 0 ? y[1][0] : (t == 1 ? y[2][2] : 0.f);
        if (t < 3) {
            float4 old;
            asm volatile("atom.relaxed.gpu.global.add.v4.f32 {%0,%1,%2,%3}, [%4], {%5,%6,%7,%8};"
                         : "=f"(old.x), "=f"(old.y), "=f"(old.z), "=f"(old.w)
                         : "l"(&g_accC[vidx]), "f"(v0), "f"(v1), "f"(v2), "f"(1.0f) : "memory");
            if (old.w == (float)(kNFFN - 1)) {
                float tot[3] = {old.x + v0, old.y + v1, old.z + v2};
#pragma unroll
                for (int i = 0; i < 3; i++) {
                    int j = 3 * t + i;
                    if (j < 8)
                        out[64 * warp + 16 * (j >> 1) + 8 * (j & 1) + g] =
                            __float2bfloat16_rn(x1o[i] + rbf(gbo[i] * rbf(tot[i])));
                }
            }
        }
    }
    TS(15);
}

typedef CUresult (*EncodeFn)(CUtensorMap*, CUtensorMapDataType, cuuint32_t, void*, const cuuint64_t*, const cuuint64_t*,
                             const cuuint32_t*, const cuuint32_t*, CUtensorMapInterleave, CUtensorMapSwizzle,
                             CUtensorMapL2promotion, CUtensorMapFloatOOBfill);

void encode(EncodeFn fn, CUtensorMap* m, const void* p, int rank, const cuuint64_t* dims, const cuuint64_t* strides,
            const cuuint32_t* box, CUtensorMapSwizzle sw) {
    cuuint32_t es[3] = {1, 1, 1};
    fn(m, CU_TENSOR_MAP_DATA_TYPE_BFLOAT16, rank, const_cast<void*>(p), dims, strides, box, es,
       CU_TENSOR_MAP_INTERLEAVE_NONE, sw, CU_TENSOR_MAP_L2_PROMOTION_L2_256B, CU_TENSOR_MAP_FLOAT_OOB_FILL_NONE);
}

}

extern "C" void kernel_launch(void* const* d_in, const int* in_sizes, int n_in, void* d_out, int out_size) {
    (void)in_sizes; (void)n_in; (void)out_size;
    static EncodeFn fn = nullptr;
    if (!fn) {
        cudaDriverEntryPointQueryResult qr;
        cudaGetDriverEntryPoint("cuTensorMapEncodeTiled", (void**)&fn, cudaEnableDefault, &qr);
        cudaFuncSetAttribute(fused_kernel, cudaFuncAttributeMaxDynamicSharedMemorySize, SM_ALLOC);
    }
    Maps maps;
    {
        cuuint64_t d[2] = {4096, 512}, s[1] = {8192};
        cuuint32_t bx[2] = {32, 256};
        encode(fn, &maps.wq, d_in[3], 2, d, s, bx, CU_TENSOR_MAP_SWIZZLE_64B);
    }
    {
        cuuint64_t d[2] = {128, 32 * 4096}, s[1] = {256};
        cuuint32_t bx[2] = {32, 256};
        encode(fn, &maps.v, d_in[2], 2, d, s, bx, CU_TENSOR_MAP_SWIZZLE_64B);
    }
    {
        cuuint64_t d[3] = {64, 4096, 8}, s[2] = {1024, 128};
        cuuint32_t bx[3] = {64, 32, 4};
        encode(fn, &maps.wo, d_in[4], 3, d, s, bx, CU_TENSOR_MAP_SWIZZLE_128B);
    }
    {
        cuuint64_t d[2] = {kF, 512}, s[1] = {kF * 2};
        cuuint32_t bx[2] = {16, 256};
        encode(fn, &maps.wg, d_in[6], 2, d, s, bx, CU_TENSOR_MAP_SWIZZLE_32B);
        encode(fn, &maps.wu, d_in[7], 2, d, s, bx, CU_TENSOR_MAP_SWIZZLE_32B);
    }
    {
        cuuint64_t d[3] = {64, kF, 8}, s[2] = {1024, 128};
        cuuint32_t bx[3] = {64, 16, 8};
        encode(fn, &maps.wd, d_in[8], 3, d, s, bx, CU_TENSOR_MAP_SWIZZLE_128B);
    }
    fused_kernel<<<kNCTA, kThreads, SM_ALLOC, cudaStreamPerThread>>>(
        maps, (const __nv_bfloat16*)d_in[0], (const __nv_bfloat16*)d_in[1], (const __nv_bfloat16*)d_in[9],
        (const __nv_bfloat16*)d_in[10], (__nv_bfloat16*)d_out);
}
```

```cpp
#include <cuda_runtime.h>
#include <cuda_bf16.h>
#include <cuda.h>
#include <stdint.h>

namespace {

constexpr int kD = 512;
constexpr int kF = 1376;
constexpr int kNCTA = 128;
constexpr int kNFFN = 86;
constexpr int kStage = 16384;
constexpr int kRing = 13;
constexpr int kTau = 1290;
constexpr int kT0 = -2300;
constexpr int kWinMin = 2, kWinMax = 6, kWinFfn = 3;
constexpr int kHelpers = 3;
constexpr int kThreads = (9 + kHelpers) * 32;
constexpr unsigned kSpinMax = 1u << 22;

constexpr int E_K = 3;
constexpr int E_L = 19;
constexpr int E_V0 = 20;
constexpr int E_WO = 36;
constexpr int E_FFN = 38;
constexpr int E_END = E_FFN + 3;

constexpr int SM_RING = 0;
constexpr int SM_P = kRing * kStage;
constexpr int SM_OX = SM_P + 4096;
constexpr int SM_RED = SM_OX + 2048;
constexpr int SM_BC = SM_RED + 2048;
constexpr int SM_STAT = SM_BC + 2048;
constexpr int SM_DUMMY = SM_STAT + 256;
constexpr int SM_BAR = SM_DUMMY + (SM_DUMMY - SM_RED);
constexpr int SM_TOTAL = SM_BAR + (2 * kRing + 1) * 8;
constexpr int SM_ALLOC = SM_TOTAL + 128;

struct Maps {
    CUtensorMap we, wq, wl, v, wo, wg, wu;
};

typedef unsigned long long u64;
constexpr int kAccSize = 64 * 128;
__host__ __device__ constexpr int acc_index(int v) { return (v >> 2) * 128 + (v & 3); }
constexpr int kScratchAlign = 131072;
struct __align__(4096) Scratch {
    float4 accB[kAccSize];
    float4 accC[kAccSize];
    u64 mod[128 * 32];
    u64 q[32 * 64];
    u64 sc[32 * 2048];
    unsigned int epoch, zeroed;
};
__device__ __align__(4096) unsigned char g_s[sizeof(Scratch) + kScratchAlign];

__device__ __forceinline__ uint32_t smem_u32(const void* p) { return (uint32_t)__cvta_generic_to_shared(p); }
__device__ __forceinline__ void mbar_init(uint32_t bar, int cnt) {
    asm volatile("mbarrier.init.shared::cta.b64 [%0], %1;" ::"r"(bar), "r"(cnt) : "memory");
}
__device__ __forceinline__ void mbar_expect_tx(uint32_t bar, uint32_t bytes) {
    asm volatile("mbarrier.arrive.expect_tx.shared::cta.b64 _, [%0], %1;" ::"r"(bar), "r"(bytes) : "memory");
}
__device__ __forceinline__ void mbar_arrive(uint32_t bar, uint32_t n, bool pred) {
    asm volatile("{\n.reg .pred p;\nsetp.ne.u32 p, %2, 0;\n@p mbarrier.arrive.shared::cta.b64 _, [%0], %1;\n}"
                 ::"r"(bar), "r"(n), "r"((uint32_t)pred) : "memory");
}
__device__ __forceinline__ bool mbar_test(uint32_t bar, uint32_t parity) {
    uint32_t ok;
    asm volatile("{\n.reg .pred p;\nmbarrier.test_wait.parity.shared::cta.b64 p, [%1], %2;\nselp.u32 %0, 1, 0, p;\n}"
                 : "=r"(ok) : "r"(bar), "r"(parity) : "memory");
    return ok;
}
__device__ __forceinline__ void mbar_wait(uint32_t bar, uint32_t parity) {
    uint32_t ok;
    unsigned spins = 0;
    do {
        asm volatile("{\n.reg .pred p;\nmbarrier.try_wait.parity.shared::cta.b64 p, [%1], %2;\nselp.u32 %0, 1, 0, p;\n}"
                     : "=r"(ok) : "r"(bar), "r"(parity) : "memory");
        if (++spins > kSpinMax) __trap();
    } while (!ok);
}
__device__ __forceinline__ void bulk_load(uint32_t dst, const void* src, uint32_t bytes, uint32_t bar, uint64_t pol) {
    asm volatile("cp.async.bulk.shared::cluster.global.mbarrier::complete_tx::bytes.L2::cache_hint [%0], [%1], %2, [%3], %4;"
                 ::"r"(dst), "l"(src), "r"(bytes), "r"(bar), "l"(pol) : "memory");
}
__device__ __forceinline__ void tma2d(uint32_t dst, const CUtensorMap* m, int c0, int c1, uint32_t bar) {
    asm volatile("cp.async.bulk.tensor.2d.shared::cluster.global.mbarrier::complete_tx::bytes [%0], [%1, {%3, %4}], [%2];"
                 ::"r"(dst), "l"(m), "r"(bar), "r"(c0), "r"(c1) : "memory");
}
__device__ __forceinline__ void tma2d_h(uint32_t dst, const CUtensorMap* m, int c0, int c1, uint32_t bar, uint64_t pol) {
    asm volatile("cp.async.bulk.tensor.2d.shared::cluster.global.mbarrier::complete_tx::bytes.L2::cache_hint [%0], [%1, {%3, %4}], [%2], %5;"
                 ::"r"(dst), "l"(m), "r"(bar), "r"(c0), "r"(c1), "l"(pol) : "memory");
}
__device__ __forceinline__ uint32_t lds32(uint32_t addr) {
    uint32_t v;
    asm volatile("ld.shared.u32 %0, [%1];" : "=r"(v) : "r"(addr) : "memory");
    return v;
}
__device__ __forceinline__ uint4 lds128(uint32_t addr) {
    uint4 v;
    asm volatile("ld.shared.v4.u32 {%0,%1,%2,%3}, [%4];" : "=r"(v.x), "=r"(v.y), "=r"(v.z), "=r"(v.w) : "r"(addr) : "memory");
    return v;
}
__device__ __forceinline__ float4 lds128f(uint32_t addr) {
    float4 v;
    asm volatile("ld.shared.v4.f32 {%0,%1,%2,%3}, [%4];" : "=f"(v.x), "=f"(v.y), "=f"(v.z), "=f"(v.w) : "r"(addr) : "memory");
    return v;
}
__device__ __forceinline__ void sts16(uint32_t addr, uint32_t v) {
    asm volatile("st.shared.u16 [%0], %1;" ::"r"(addr), "h"((unsigned short)v) : "memory");
}
__device__ __forceinline__ void sts32(uint32_t addr, float v) {
    asm volatile("st.shared.f32 [%0], %1;" ::"r"(addr), "f"(v) : "memory");
}
__device__ __forceinline__ void sts64(uint32_t addr, float a, float b) {
    asm volatile("st.shared.v2.f32 [%0], {%1,%2};" ::"r"(addr), "f"(a), "f"(b) : "memory");
}
template <int ID>
__device__ __forceinline__ void bar_with_producer(bool pred) {
    asm volatile("{\n.reg .pred p;\nsetp.ne.u32 p, %0, 0;\n@p bar.sync %1, 288;\n}" ::"r"((uint32_t)pred), "n"(ID) : "memory");
}
__device__ __forceinline__ void bar_consumers(bool pred) {
    asm volatile("{\n.reg .pred p;\nsetp.ne.u32 p, %0, 0;\n@p bar.sync 1, 256;\n}" ::"r"((uint32_t)pred) : "memory");
}
template <class T>
__device__ __forceinline__ T pin(T v, int lane) { return __shfl_sync(0xffffffffu, v, lane); }
__device__ __forceinline__ float shx(float v, int m) { return __shfl_xor_sync(0xffffffffu, v, m); }

__device__ __forceinline__ float bf_lo(uint32_t v) { return __uint_as_float(v << 16); }
__device__ __forceinline__ float bf_hi(uint32_t v) { return __uint_as_float(v & 0xffff0000u); }
__device__ __forceinline__ uint32_t pack_bf(float lo, float hi) {
    uint32_t r;
    asm("cvt.rn.bf16x2.f32 %0, %1, %2;" : "=r"(r) : "f"(hi), "f"(lo));
    return r;
}
__device__ __forceinline__ float rbf(float x) { return bf_hi(pack_bf(0.f, x)); }
__device__ __forceinline__ uint32_t bf2_add(uint32_t a, uint32_t b) {
    uint32_t r;
    asm("add.rn.bf16x2 %0, %1, %2;" : "=r"(r) : "r"(a), "r"(b));
    return r;
}
__device__ __forceinline__ uint32_t bf2_sub(uint32_t a, uint32_t b) {
    uint32_t r;
    asm("sub.rn.bf16x2 %0, %1, %2;" : "=r"(r) : "r"(a), "r"(b));
    return r;
}
__device__ __forceinline__ uint32_t bf2_mul(uint32_t a, uint32_t b) {
    uint32_t r;
    asm("mul.rn.bf16x2 %0, %1, %2;" : "=r"(r) : "r"(a), "r"(b));
    return r;
}

__device__ __forceinline__ uint32_t next_flag(uint32_t epoch) { return epoch + 1 + (epoch == 0xffffffffu); }
__device__ __forceinline__ void ll_store(u64* p, uint32_t data, uint32_t flag, bool pred) {
    u64 v = ((u64)flag << 32) | data;
    asm volatile("{\n.reg .pred p;\nsetp.ne.u32 p, %2, 0;\n@p st.relaxed.gpu.global.b64 [%0], %1;\n}"
                 ::"l"(p), "l"(v), "r"((uint32_t)pred) : "memory");
}
__device__ __forceinline__ void clear16(void* p) {
    asm volatile("st.relaxed.gpu.global.v2.b64 [%0], {%1,%1};" ::"l"(p), "l"(0ull) : "memory");
}
__device__ __forceinline__ bool ll_poll2(const u64* p, uint32_t flag, u64& a, u64& b) {
    asm volatile("{\n.reg .pred p;\n.reg .b32 lo, ha, hb;\nmov.b64 {lo, ha}, %0;\nmov.b64 {lo, hb}, %1;\n"
                 "setp.ne.u32 p, ha, %3;\nsetp.ne.or.u32 p, hb, %3, p;\n"
                 "@p ld.relaxed.gpu.global.v2.b64 {%0,%1}, [%2];\n}"
                 : "+l"(a), "+l"(b) : "l"(p), "r"(flag) : "memory");
    return (uint32_t)(a >> 32) == flag && (uint32_t)(b >> 32) == flag;
}
__device__ __forceinline__ bool ll_poll1(const u64* p, uint32_t flag, u64& a) {
    asm volatile("{\n.reg .pred p;\n.reg .b32 lo, ha;\nmov.b64 {lo, ha}, %0;\n"
                 "setp.ne.u32 p, ha, %2;\n@p ld.relaxed.gpu.global.b64 %0, [%1];\n}"
                 : "+l"(a) : "l"(p), "r"(flag) : "memory");
    return (uint32_t)(a >> 32) == flag;
}
__device__ __forceinline__ bool poll_done(bool ok, unsigned& spins) {
    if (__all_sync(0xffffffffu, ok)) return true;
    if (++spins > kSpinMax) __trap();
    __nanosleep(100);
    return false;
}
template <int STRIDE = 128>
__device__ __forceinline__ float sum8(uint32_t addr) {
    float v[8];
#pragma unroll
    for (int i = 0; i < 8; i++) v[i] = __uint_as_float(lds32(addr + i * STRIDE));
    return ((v[0] + v[1]) + (v[2] + v[3])) + ((v[4] + v[5]) + (v[6] + v[7]));
}

__device__ __forceinline__ void ln_part(uint32_t v2, uint32_t dst) {
    float a = bf_lo(v2), c = bf_hi(v2);
    float shift = __shfl_sync(0xffffffffu, a, 0);
    a -= shift;
    c -= shift;
    float s = a + c, ss = fmaf(a, a, c * c);
#pragma unroll
    for (int o = 16; o >= 1; o >>= 1) {
        s += shx(s, o);
        ss += shx(ss, o);
    }
    float md = s * (1.f / 64.f);
    sts64(dst, shift + md, fmaf(-s, md, ss));
}
__device__ __forceinline__ uint32_t ln_apply(uint32_t v2, uint32_t src, uint32_t cs1, uint32_t sh) {
    float4 p0 = lds128f(src), p1 = lds128f(src + 16), p2 = lds128f(src + 32), p3 = lds128f(src + 48);
    float d1 = p0.z - p0.x, d2 = p1.x - p0.x, d3 = p1.z - p0.x, d4 = p2.x - p0.x;
    float d5 = p2.z - p0.x, d6 = p3.x - p0.x, d7 = p3.z - p0.x;
    float ds = ((d1 + d2) + (d3 + d4)) + ((d5 + d6) + d7);
    float dd = (fmaf(d1, d1, d2 * d2) + fmaf(d3, d3, d4 * d4)) + (fmaf(d5, d5, d6 * d6) + d7 * d7);
    float m2 = ((p0.y + p0.w) + (p1.y + p1.w)) + ((p2.y + p2.w) + (p3.y + p3.w));
    float md = ds * 0.125f;
    float var = fmaxf(fmaf(fmaf(-ds, md, dd), 64.f, m2) * (1.f / kD), 0.f);
    float mean = p0.x + md;
    float den, rcp;
    asm("sqrt.approx.ftz.f32 %0, %1;" : "=f"(den) : "f"(rbf(rbf(var) + 1e-5f)));
    asm("rcp.approx.ftz.f32 %0, %1;" : "=f"(rcp) : "f"(rbf(den)));
    uint32_t d = bf2_sub(v2, pack_bf(mean, mean));
    uint32_t n = pack_bf(bf_lo(d) * rcp, bf_hi(d) * rcp);
    return bf2_add(bf2_mul(n, cs1), sh);
}

__global__ void __cluster_dims__(2, 1, 1) __launch_bounds__(kThreads, 1)
fused_kernel(const char* __restrict__ kc, const uint32_t* __restrict__ x, const uint32_t* __restrict__ cvec,
             uint32_t* __restrict__ out, Scratch* __restrict__ S,
             const char* __restrict__ wd_p, const __grid_constant__ Maps maps) {
    extern __shared__ uint8_t smem_raw[];
    int tid = threadIdx.x;
    asm volatile("" : "+r"(tid));
    const int lane = tid & 31;
    const int warp = __shfl_sync(0xffffffffu, tid >> 5, 0);
    const int b = blockIdx.x, h = b >> 2;
    uint32_t sbase = (smem_u32(smem_raw) + 127u) & ~127u;
    asm volatile("" : "+r"(sbase));
    const uint32_t bar_full = sbase + SM_BAR, bar_empty = bar_full + kRing * 8, bar_ox = bar_empty + kRing * 8;
    const bool is_ffn = b < kNFFN;

    uint32_t t_start;
    asm volatile("mov.u32 %0, %clock;" : "=r"(t_start));
    if (tid == 256) {
#pragma unroll
        for (int i = 0; i <= E_K; i++) mbar_init(bar_full + i * 8, 1);
        asm volatile("fence.mbarrier_init.release.cluster;" ::: "memory");
        uint64_t pol;
        asm volatile("createpolicy.fractional.L2::evict_first.b64 %0, 1.0;" : "=l"(pol));
        mbar_expect_tx(bar_full + E_K * 8, kStage);
        bulk_load(sbase + E_K * kStage, kc + (size_t)b * 16 * kStage, kStage, bar_full + E_K * 8, pol);
        mbar_expect_tx(bar_full, 8192);
        tma2d(sbase, &maps.we, b * 8, 0, bar_full);
        tma2d(sbase + 4096, &maps.we, b * 8, 256, bar_full);
        mbar_expect_tx(bar_full + 8, kStage);
        tma2d(sbase + kStage, &maps.wq, b * 32, 0, bar_full + 8);
        mbar_expect_tx(bar_full + 16, kStage);
        tma2d(sbase + 2 * kStage, &maps.wq, b * 32, 256, bar_full + 16);
    }

    if (warp == 8) {
        __syncwarp();
        if (lane < kRing) {
            if (lane > E_K) mbar_init(bar_full + lane * 8, 1);
            mbar_init(bar_empty + lane * 8, 8);
            if (lane == 0) {
                mbar_init(bar_ox, 1);
                mbar_expect_tx(bar_ox, 2048);
            }
            asm volatile("fence.mbarrier_init.release.cluster;" ::: "memory");
        } else if (lane >= 27) {
            asm volatile("prefetch.tensormap [%0];" ::"l"(&maps.wl + (lane - 27)) : "memory");
        }
        __syncwarp();
        asm volatile("bar.arrive 2, 288;" ::: "memory");
        asm volatile("barrier.cluster.arrive.relaxed.aligned;" ::: "memory");
        const int n_ent = is_ffn ? E_END : E_FFN;
        int s = E_K + 1, ph = 0;
        uint64_t pol;
        asm volatile("createpolicy.fractional.L2::evict_first.b64 %0, 1.0;" : "=l"(pol));
#pragma unroll 1
        for (int e = E_K + 1; e < n_ent; e++) {
            const uint32_t dst = sbase + SM_RING + s * kStage, bar = bar_full + s * 8;
            const char* src = nullptr;
            const CUtensorMap* m = &maps.v;
            int c0 = (b & 2) * 32, c1 = h * 4096 + (b & 1) * 2048 + (e - E_V0) * 128;
            if (e < E_V0) src = kc + (size_t)(b * 16 + e - E_K) * kStage;
            if (e >= E_WO) {
                m = &maps.wo;
                c0 = (b & 1) * 256;
                c1 = (b >> 1) * 64 + (e - E_WO) * 32;
            }
            if (e == E_FFN + 2) src = wd_p + b * 16384;
            const bool two = e == E_L || e == E_FFN || e == E_FFN + 1;
            if (two) {
                m = e == E_L ? &maps.wl : (e == E_FFN ? &maps.wg : &maps.wu);
                c0 = b * 16 + (e == E_L ? 1024 : 0);
            }
            int sl = s - 1 - lane, pl = ph;
            if (sl < 0) { sl += kRing; pl ^= 1; }
            const bool watch = lane < 8 && lane < e;
            unsigned spins = 0;
            while (true) {
                const bool pending = watch && !mbar_test(bar_full + sl * 8, pl);
                const int inflight = __popc(__ballot_sync(0xffffffffu, pending));
                uint32_t now;
                asm volatile("mov.u32 %0, %clock;" : "=r"(now));
                const int lag = (int)(now - t_start) - kT0 - (e + inflight - 2) * kTau;
                if (e >= E_FFN ? inflight < kWinFfn : (inflight < kWinMin || (inflight < kWinMax && lag >= 0))) break;
                if (++spins > kSpinMax) __trap();
            }
            if (e >= kRing) mbar_wait(bar_empty + s * 8, ph ^ 1);
            if (lane == 0) {
                mbar_expect_tx(bar, kStage);
                if (two) {
                    tma2d(dst, m, c0, 0, bar);
                    tma2d(dst + 8192, m, c0, 256, bar);
                } else if (src) {
                    bulk_load(dst, src, kStage, bar, pol);
                } else {
                    tma2d_h(dst, m, c0, c1, bar, pol);
                }
            }
            __syncwarp();
            if (++s == kRing) { s = 0; ph ^= 1; }
        }
        if (is_ffn) {
            mbar_wait(bar_full + ((E_FFN + 1) % kRing) * 8, ((E_FFN + 1) / kRing) & 1);
            __syncwarp();
            asm volatile("bar.arrive 4, 288;" ::: "memory");
            mbar_wait(bar_full + ((E_FFN + 2) % kRing) * 8, ((E_FFN + 2) / kRing) & 1);
            __syncwarp();
            asm volatile("bar.arrive 5, 288;" ::: "memory");
        }
        return;
    }

    const bool live = warp < 8;
    const int hid = warp - 9;
    const int w = warp & 7;
    const int pair = w * 32 + lane;
    const bool lead = live && lane == 0;
    asm volatile("barrier.cluster.arrive.relaxed.aligned;" ::: "memory");

    uint32_t flag = 0, xp = 0, cp = 0;
    if (live) {
        cp = __ldg(cvec + pair);
        xp = __ldg(x + pair);
        asm volatile("ld.relaxed.gpu.global.u32 %0, [%1];" : "=r"(flag) : "l"(&S->epoch) : "memory");
        if (tid < 2) clear16(&S->mod[b * 32 + tid * 2]);
        else if (tid < 6) clear16(&S->mod[b * 32 + 16 + (tid - 2) * 2]);
        else if (tid < 14) clear16(&S->q[b * 16 + (tid - 6) * 2]);
        clear16(&S->sc[b * 512 + tid * 2]);
        ln_part(xp, sbase + SM_STAT + w * 8);
        float c0 = bf_lo(cp), c1 = bf_hi(cp);
        cp = pack_bf(__fdividef(c0, 1.f + __expf(-c0)), __fdividef(c1, 1.f + __expf(-c1)));
        flag = next_flag(flag);
        asm volatile("bar.sync 2, 288;" ::: "memory");
    }

    const u64 inval = (u64)(~flag) << 32;
    float4* accp = (float4*)pin((u64)&S->accB[acc_index(pair)], lane);
    uint32_t* outp = (uint32_t*)pin((u64)(out + pair), lane);
    const int blane = pin(b * 32 + lane, lane);
    const uint32_t wbase = sbase + (live ? 0 : SM_DUMMY - SM_RED);
    uint32_t bc = wbase + SM_BC + w * 256, redb = wbase + SM_RED, redw = redb + w * 128, stat = wbase + SM_STAT;
    const uint32_t lane4 = pin(lane * 4, lane);

#pragma unroll 1
    for (int round = live ? 0 : (hid < 2 ? hid : 3); round < 3; round++) {
        if (round == 2) {
            u64 qq[4];
#pragma unroll
            for (int i = 0; i < 4; i++) qq[i] = inval;
            if (live) {
                unsigned spins = 0;
                bool ok;
                do {
                    const u64* p = &S->q[h * 64 + (lane & 15) * 4];
                    ok = ll_poll2(p, flag, qq[0], qq[1]);
                    ok &= ll_poll2(p + 2, flag, qq[2], qq[3]);
                } while (!poll_done(ok, spins));
            }
            float q[8];
#pragma unroll
            for (int i = 0; i < 4; i++) { q[2 * i] = bf_lo((uint32_t)qq[i]); q[2 * i + 1] = bf_hi((uint32_t)qq[i]); }
#pragma unroll 1
            for (int j = 0; j < 2; j++) {
                const int ent = E_K + w + 8 * j, stg = ent >= kRing ? ent - kRing : ent;
                if (live) {
                    if (ent >= kRing) mbar_wait(bar_empty + stg * 8, 0);
                    mbar_wait(bar_full + stg * 8, ent >= kRing);
                }
                float s0 = 0.f, s1 = 0.f;
#pragma unroll 1
                for (int grp = 0; grp < 4; grp++) {
                    const uint32_t base = sbase + SM_RING + stg * kStage + (grp >> 1) * 8192 + (grp & 1) * 2048 + lane * 16;
                    float d[8];
#pragma unroll
                    for (int i = 0; i < 8; i++) {
                        uint4 k = lds128(base + (i & 3) * 512 + (i >> 2) * 4096);
                        float e = bf_lo(k.x) * q[0], o = bf_hi(k.x) * q[1];
                        e = fmaf(bf_lo(k.y), q[2], e); o = fmaf(bf_hi(k.y), q[3], o);
                        e = fmaf(bf_lo(k.z), q[4], e); o = fmaf(bf_hi(k.z), q[5], o);
                        e = fmaf(bf_lo(k.w), q[6], e); o = fmaf(bf_hi(k.w), q[7], o);
                        d[i] = e + o;
                    }
#pragma unroll
                    for (int st = 4; st >= 1; st >>= 1) {
                        const bool up = (lane & (2 * st)) != 0;
#pragma unroll
                        for (int i = 0; i < st; i++) {
                            float send = up ? d[i] : d[i + st], keep = up ? d[i + st] : d[i];
                            d[i] = keep + shx(send, 2 * st);
                        }
                    }
                    d[0] += shx(d[0], 1);
                    if ((lane & 1) == (grp >> 1)) {
                        if (grp & 1) s1 = d[0]; else s0 = d[0];
                    }
                    if (!live) break;
                }
                __syncwarp();
                mbar_arrive(bar_empty + stg * 8, 8, lead);
                const float scale = 0.08838834764831845f;
                uint32_t s2 = pack_bf(s0, s1);
                s2 = pack_bf(bf_lo(s2) * scale, bf_hi(s2) * scale);
                const int pos = (lane & 1) * 16 + (lane & 8) + (lane >> 4) * 4 + ((lane >> 1) & 3);
                if (!live) {
                    sts32(bc, __uint_as_float(s2));
                    break;
                }
                ll_store(&S->sc[b * 512 + (w + 8 * j) * 32 + pos], s2, flag, true);
            }
            if (b == kNCTA - 1 && warp == 0) asm volatile("bar.arrive 3, 64;" ::: "memory");
            if (!live) break;
        }
        const int rl = round == 0 ? 3 : (round == 2 ? 2 : 1);
        uint32_t val = cp;
        if (round == 1) {
            u64 sa = inval, ca = inval;
            if (live) {
                unsigned spins = 0;
                bool ok;
                do {
                    const u64* p = &S->mod[(pair >> 2) * 32 + (pair & 3)];
                    ok = ll_poll1(p, flag, sa);
                    ok &= ll_poll1(p + 64 * 32, flag, ca);
                } while (!poll_done(ok, spins));
            }
            val = ln_apply(xp, sbase + SM_STAT, bf2_add((uint32_t)ca, 0x3f803f80u), (uint32_t)sa);
        }
        const int r = 2 * lane, idx = (r >> rl) & 7;
        const uint32_t a = bc + ((((r >> (rl + 3)) << rl) + (r & ((1 << rl) - 1))) << 4) + (idx & 3) * 4 + (idx >> 2) * 2;
        sts16(a, val);
        sts16(a + 16, val >> 16);
        __syncwarp();
        if (hid == 1) continue;
        const int st = round == 0 ? 0 : (round == 2 ? E_L - kRing : 1 + (w >> 2));
        if (live) {
            if (round == 2) mbar_wait(bar_empty + st * 8, 0);
            mbar_wait(bar_full + st * 8, round == 2);
        }
        uint32_t ta = sbase + SM_RING + (round == 2 ? E_L - kRing : round) * kStage + (w << (13 - rl)) + lane * 4;
        uint32_t pa = bc + ((lane >> (5 - rl)) << 4);
        float a0 = 0.f, a1 = 0.f;
#pragma unroll 1
        for (int sgm = 0; sgm < (8 >> rl); sgm++) {
            const uint4 pw = lds128(pa);
            const uint32_t pv[4] = {pw.x, pw.y, pw.z, pw.w};
#pragma unroll
            for (int i = 0; i < 4; i++) {
                const uint32_t v0 = lds32(ta + i * 128), v1 = lds32(ta + i * 128 + 512);
                a0 = fmaf(bf_lo(pv[i]), bf_lo(v0), a0); a1 = fmaf(bf_lo(pv[i]), bf_hi(v0), a1);
                a0 = fmaf(bf_hi(pv[i]), bf_lo(v1), a0); a1 = fmaf(bf_hi(pv[i]), bf_hi(v1), a1);
            }
            ta += 1024;
            pa += 16 << rl;
        }
        __syncwarp();
        mbar_arrive(bar_empty + st * 8, round == 1 ? 2 : 1, lead);
#pragma unroll 1
        for (int o = 16; o >= (32 >> rl); o >>= 1) { a0 += shx(a0, o); a1 += shx(a1, o); }
        const uint32_t red = redb + (round & 1) * 1024;
        sts64(red + w * 128 + (lane & 15) * 8, a0, a1);
        bar_consumers(live);
        const float sum = sum8(red + lane * 4);
        const uint32_t pk = pack_bf(sum, __shfl_down_sync(0xffffffffu, sum, 1));
        u64* dst = round == 1 ? &S->q[b * 16] : &S->mod[b * 32 + round * 8];
        ll_store(dst + (lane >> 1), pk, flag, warp == 0 && !(lane & 1) && lane < (64 >> rl));
        if (!live) {
            if (b == kNCTA - 1) {
                asm volatile("ld.relaxed.gpu.global.u32 %0, [%1];" : "=r"(flag) : "l"(&S->epoch) : "memory");
                asm volatile("bar.sync 3, 64;" ::: "memory");
#pragma unroll 1
                for (int i = 0; i < 16; i++) clear16(&S->accB[(i >> 3) * kAccSize + acc_index((i & 7) * 32 + lane)]);
                __syncwarp();
                if (lane == 0) asm volatile("st.release.gpu.global.u32 [%0], %1;" ::"l"(&S->zeroed), "r"(next_flag(flag)) : "memory");
            }
            return;
        }
    }

    uint32_t ga = 0, gb = 0, sb = 0, cb1 = 0;
    float acc[4] = {0.f, 0.f, 0.f, 0.f};
    if (hid != 2) {
        {
            u64 sv[8];
#pragma unroll
            for (int i = 0; i < 8; i++) sv[i] = inval;
            const int unit = (lane >> 2) * 64 + 8 * w + 2 * (lane & 3);
            if (live) {
                unsigned spins = 0;
                bool ok;
                const u64* p = &S->sc[h * 2048 + unit];
                do {
                    ok = true;
#pragma unroll
                    for (int i = 0; i < 4; i++) ok &= ll_poll2(p + ((i ^ ((b & 1) << 1)) * 512), flag, sv[2 * i], sv[2 * i + 1]);
                } while (!poll_done(ok, spins));
                asm volatile("barrier.cluster.wait.acquire.aligned;" ::: "memory");
            }
            float e[16];
#pragma unroll
            for (int i = 0; i < 8; i++) { e[2 * i] = bf_lo((uint32_t)sv[i]); e[2 * i + 1] = bf_hi((uint32_t)sv[i]); }
            float m = e[0];
#pragma unroll
            for (int i = 1; i < 16; i++) m = fmaxf(m, e[i]);
#pragma unroll
            for (int o = 16; o >= 1; o >>= 1) m = fmaxf(m, shx(m, o));
            sts32(stat + 64 + w * 4, m);
            bar_consumers(live);
            {
                float4 m0 = lds128f(stat + 64), m1 = lds128f(stat + 80);
                m = fmaxf(fmaxf(fmaxf(m0.x, m0.y), fmaxf(m0.z, m0.w)), fmaxf(fmaxf(m1.x, m1.y), fmaxf(m1.z, m1.w)));
            }
            float sum = 0.f;
            const float kLog2e = 1.4426950408889634f;
#pragma unroll
            for (int i = 0; i < 16; i++) {
                asm("ex2.approx.ftz.f32 %0, %1;" : "=f"(e[i]) : "f"((e[i] - m) * kLog2e));
                sum += e[i];
            }
#pragma unroll
            for (int o = 16; o >= 1; o >>= 1) sum += shx(sum, o);
            sts32(stat + 96 + w * 4, sum);
            bar_consumers(live);
            {
                float4 m0 = lds128f(stat + 96), m1 = lds128f(stat + 112);
                sum = ((m0.x + m0.y) + (m0.z + m0.w)) + ((m1.x + m1.y) + (m1.z + m1.w));
            }
            const float inv = __fdividef(1.f, sum);
#pragma unroll
            for (int i = 0; i < 2; i++) {
                uint32_t v0 = pack_bf(e[4 * i] * inv, e[4 * i + 1] * inv), v1 = pack_bf(e[4 * i + 2] * inv, e[4 * i + 3] * inv);
                sts64(live ? sbase + SM_P + unit * 4 + i * 2048 : bc, __uint_as_float(v0), __uint_as_float(v1));
            }
            __syncwarp();
        }

        int st = E_V0 - kRing, ph = 1;
        uint32_t paddr = sbase + SM_P + w * 32;
        const uint32_t toff = sbase + SM_RING + w * 2048 + lane * 4;
#pragma unroll 1
        for (int j = 0; j < 16; j++) {
            if (j == 8) {
                if (live) {
                    unsigned spins = 0;
                    bool ok;
                    u64 m0 = inval, m1 = inval, m2 = inval, m3 = inval;
                    do {
                        const u64* p = &S->mod[(pair >> 3) * 32 + 16 + (pair & 7)];
                        ok = ll_poll1(p, flag, m0);
                        ok &= ll_poll1(p + 32 * 32, flag, m1);
                        ok &= ll_poll1(p + 64 * 32, flag, m2);
                        ok &= ll_poll1(p + 96 * 32, flag, m3);
                        uint32_t z;
                        asm volatile("ld.acquire.gpu.global.u32 %0, [%1];" : "=r"(z) : "l"(&S->zeroed) : "memory");
                        ok &= z == flag;
                    } while (!poll_done(ok, spins));
                    if (b == 0 && tid == 0) S->epoch = flag;
                    ga = (uint32_t)m0; sb = (uint32_t)m1; cb1 = bf2_add((uint32_t)m2, 0x3f803f80u); gb = (uint32_t)m3;
                }
            }
            float p[16];
            {
                uint4 pa = lds128(paddr), pb = lds128(paddr + 16);
                const uint32_t pw[8] = {pa.x, pa.y, pa.z, pa.w, pb.x, pb.y, pb.z, pb.w};
#pragma unroll
                for (int i = 0; i < 8; i++) {
                    p[2 * i] = bf_lo(pw[i]);
                    p[2 * i + 1] = bf_hi(pw[i]);
                    asm volatile("" : "+f"(p[2 * i]), "+f"(p[2 * i + 1]));
                }
            }
            uint32_t a0 = toff + st * kStage, bar = bar_full + st * 8;
            const int cph = ph;
            paddr += 256;
            if (++st == kRing) { st = 0; ph ^= 1; }
            asm volatile("" : "+r"(a0), "+r"(bar), "+r"(st), "+r"(ph), "+r"(paddr));
            if (live) mbar_wait(bar, cph);
            uint32_t v[16];
#pragma unroll
            for (int i = 0; i < 16; i++) v[i] = lds32(a0 + (i >> 3) * 128 + ((i >> 1) & 3) * 256 + (i & 1) * 1024);
            __syncwarp();
            mbar_arrive(bar + kRing * 8, 1, lead);
#pragma unroll
            for (int i = 0; i < 16; i++) {
                acc[(i & 1) * 2] = fmaf(p[i], bf_lo(v[i]), acc[(i & 1) * 2]);
                acc[(i & 1) * 2 + 1] = fmaf(p[i], bf_hi(v[i]), acc[(i & 1) * 2 + 1]);
            }
            if (!live) {
                sts64(bc, acc[0] + acc[1], acc[2] + acc[3]);
                return;
            }
        }
    }

    {
        const float a0 = acc[0] + acc[2], a1 = acc[1] + acc[3];
        if (live) {
            uint32_t ox_dst, ox_bar;
            asm("mapa.shared::cluster.u32 %0, %1, %2;" : "=r"(ox_dst) : "r"(sbase + SM_OX + w * 256 + lane * 8), "r"((b & 1) ^ 1));
            asm("mapa.shared::cluster.u32 %0, %1, %2;" : "=r"(ox_bar) : "r"(bar_ox), "r"((b & 1) ^ 1));
            asm volatile("st.async.shared::cluster.mbarrier::complete_tx::bytes.v2.f32 [%0], {%1,%2}, [%3];"
                         ::"r"(ox_dst), "f"(a0), "f"(a1), "r"(ox_bar) : "memory");
        }
        sts64(redb + w * 256 + lane * 8, a0, a1);
        bar_consumers(live);
    }
    if (w < 4) {
        if (live) {
            uint32_t ok;
            unsigned spins = 0;
            do {
                asm volatile("{\n.reg .pred p;\nmbarrier.try_wait.parity.acquire.cluster.shared::cta.b64 p, [%1], 0;\nselp.u32 %0, 1, 0, p;\n}"
                             : "=r"(ok) : "r"(bar_ox) : "memory");
                if (++spins > kSpinMax) __trap();
            } while (!ok);
        }
#pragma unroll 1
        for (int i = 0; i < 2; i++) {
            const uint32_t off = lane4 + i * 128;
            sts32(bc + off, rbf(sum8<256>(redb + off) + sum8<256>(sbase + SM_OX + off)));
        }
        __syncwarp();
        float y[4] = {0.f, 0.f, 0.f, 0.f};
        uint32_t wa = sbase + SM_RING + (E_WO % kRing) * kStage + w * 128 + lane4;
        float4* redp = (float4*)pin((u64)&S->accB[acc_index((b & 1) * 128 + pair)], lane);
#pragma unroll 1
        for (int hf = 0; hf < 2; hf++) {
            float o[32];
#pragma unroll
            for (int i = 0; i < 8; i++) {
                float4 v = lds128f(bc + hf * 128 + i * 16);
                o[4 * i] = v.x; o[4 * i + 1] = v.y; o[4 * i + 2] = v.z; o[4 * i + 3] = v.w;
            }
            static_assert(E_WO / kRing == (E_WO + 1) / kRing, "wo stages wrap");
            if (live) mbar_wait(bar_full + (E_WO % kRing + hf) * 8, (E_WO / kRing) & 1);
            uint32_t v[32];
#pragma unroll
            for (int i = 0; i < 32; i++) v[i] = lds32(wa + i * 512);
#pragma unroll
            for (int i = 0; i < 32; i++) {
                y[(i & 1) * 2] = fmaf(o[i], bf_lo(v[i]), y[(i & 1) * 2]);
                y[(i & 1) * 2 + 1] = fmaf(o[i], bf_hi(v[i]), y[(i & 1) * 2 + 1]);
            }
            wa += kStage;
        }
        const float v0 = y[0] + y[2], v1 = y[1] + y[3];
        if (!live) sts64(bc, v0, v1);
        else asm volatile("red.relaxed.gpu.global.add.v4.f32 [%0], {%1,%2,%3,%4};"
                          ::"l"(redp), "f"(v0), "f"(v1), "f"(1.0f), "f"(0.0f) : "memory");
    }
    if (blane >= kNFFN * 32) return;

    {
        constexpr int sg = E_FFN % kRing, su = (E_FFN + 1) % kRing, sd = (E_FFN + 2) % kRing;
        constexpr int pg = (E_FFN / kRing) & 1;
        float wo[64];
#pragma unroll
        for (int i = 0; i < 64; i++) wo[i] = pin(0.f + lane, lane);
        float* const wg = wo;
        float* const wu = wo + 32;
        float* const wdf = wo;
        auto load_w = [&](float* wv, uint32_t addr, int stride) {
#pragma unroll
            for (int i = 0; i < 16; i++) {
                uint32_t a = lds32(addr + i * stride);
                wv[2 * i] = bf_lo(a);
                wv[2 * i + 1] = bf_hi(a);
            }
        };
        const bool yes = __all_sync(0xffffffffu, blane >= 0);
        const uint32_t gaddr = sbase + SM_RING + w * 2048 + lane4;
        const uint32_t h2st = pin(bc + (lane & 1) * 128 + (lane >> 1) * 4, lane), h2ld = pin(bc + (lane >> 3) * 64, lane);
        const uint32_t hhst = pin(bc + (lane & 7) * 8 + ((lane >> 3) & 1) * 4, lane);
        const uint32_t gust = pin(redw + lane4, lane), guld = pin(redb + lane4, lane);
        float4 a = make_float4(0.f, 0.f, 0.f, 0.f);
        if (live) {
            unsigned spins = 0;
            bool gate;
            do {
                asm volatile("ld.relaxed.gpu.global.v4.f32 {%0,%1,%2,%3}, [%4];"
                             : "=f"(a.x), "=f"(a.y), "=f"(a.z), "=f"(a.w) : "l"(accp) : "memory");
                gate = mbar_test(bar_full + sg * 8, pg);
                if (++spins > kSpinMax) __trap();
            } while (!__all_sync(0xffffffffu, a.z == (float)(kNCTA / 2)));
            if (!gate) mbar_wait(bar_full + sg * 8, pg);
            __syncwarp();
        }
        const uint32_t x1 = bf2_add(xp, bf2_mul(ga, pack_bf(a.x, a.y)));
        if (yes) {
            load_w(wg, gaddr + sg * kStage, 128);
            ln_part(x1, stat + 128 + w * 8);
        }
        bar_with_producer<4>(live);
        if (yes) {
            const uint32_t h2 = ln_apply(x1, stat + 128, cb1, sb);
            load_w(wu, gaddr + su * kStage, 128);
            sts32(h2st, bf_lo(h2));
            sts32(h2st + 64, bf_hi(h2));
        }
        __syncwarp();
        float g0 = 0.f, g1 = 0.f, u0 = 0.f, u1 = 0.f;
#pragma unroll
        for (int i = 0; i < 4; i++) {
            float4 hv = lds128f(h2ld + i * 16);
            const float hh[4] = {hv.x, hv.y, hv.z, hv.w};
#pragma unroll
            for (int k = 0; k < 4; k++) {
                g0 = fmaf(hh[k], wg[8 * i + 2 * k], g0); g1 = fmaf(hh[k], wg[8 * i + 2 * k + 1], g1);
                u0 = fmaf(hh[k], wu[8 * i + 2 * k], u0); u1 = fmaf(hh[k], wu[8 * i + 2 * k + 1], u1);
            }
        }
        {
            const bool up = lane & 16, odd = lane & 8;
            float k0 = (up ? u0 : g0) + shx(up ? g0 : u0, 16), k1 = (up ? u1 : g1) + shx(up ? g1 : u1, 16);
            float v = (odd ? k1 : k0) + shx(odd ? k0 : k1, 8);
            sts32(gust, v);
        }
        bar_with_producer<5>(live);
        if (yes) {
            float s = rbf(sum8(guld));
            load_w(wdf, sbase + SM_RING + sd * kStage + w * 128 + lane4, 1024);
            s = rbf(s * shx(s, 16));
            sts32(hhst, s);
        }
        __syncwarp();
        float y[4] = {0.f, 0.f, 0.f, 0.f};
#pragma unroll
        for (int i = 0; i < 4; i++) {
            float4 o = lds128f(bc + i * 16);
            y[0] = fmaf(o.x, wdf[8 * i], y[0]);     y[1] = fmaf(o.x, wdf[8 * i + 1], y[1]);
            y[2] = fmaf(o.y, wdf[8 * i + 2], y[2]); y[3] = fmaf(o.y, wdf[8 * i + 3], y[3]);
            y[0] = fmaf(o.z, wdf[8 * i + 4], y[0]); y[1] = fmaf(o.z, wdf[8 * i + 5], y[1]);
            y[2] = fmaf(o.w, wdf[8 * i + 6], y[2]); y[3] = fmaf(o.w, wdf[8 * i + 7], y[3]);
        }
        const float v0 = y[0] + y[2], v1 = y[1] + y[3];
        float4 old = make_float4(0.f, 0.f, 0.f, 0.f);
        asm volatile("{\n.reg .pred p;\nsetp.ne.u32 p, %9, 0;\n@p atom.relaxed.gpu.global.add.v4.f32 {%0,%1,%2,%3}, [%4], {%5,%6,%7,%8};\n}"
                     : "+f"(old.x), "+f"(old.y), "+f"(old.z), "+f"(old.w)
                     : "l"(accp + kAccSize), "f"(v0), "f"(v1), "f"(1.0f), "f"(0.0f), "r"((uint32_t)live) : "memory");
        const uint32_t res = bf2_add(x1, bf2_mul(gb, pack_bf(old.x + v0, old.y + v1)));
        asm volatile("{\n.reg .pred p;\nsetp.ne.u32 p, %2, 0;\n@p st.global.u32 [%0], %1;\n}"
                     ::"l"(outp), "r"(res), "r"((uint32_t)(old.z == (float)(kNFFN - 1))) : "memory");
    }
}

typedef CUresult (*EncodeFn)(CUtensorMap*, CUtensorMapDataType, cuuint32_t, void*, const cuuint64_t*, const cuuint64_t*,
                             const cuuint32_t*, const cuuint32_t*, CUtensorMapInterleave, CUtensorMapSwizzle,
                             CUtensorMapL2promotion, CUtensorMapFloatOOBfill);

void encode(EncodeFn fn, CUtensorMap* m, const void* p, cuuint64_t rows, cuuint64_t cols, cuuint32_t bh, cuuint32_t bw, CUtensorMapL2promotion pr) {
    cuuint64_t dims[2] = {cols, rows}, strides[1] = {cols * 2};
    cuuint32_t box[2] = {bw, bh}, es[2] = {1, 1};
    fn(m, CU_TENSOR_MAP_DATA_TYPE_BFLOAT16, 2, const_cast<void*>(p), dims, strides, box, es, CU_TENSOR_MAP_INTERLEAVE_NONE,
       CU_TENSOR_MAP_SWIZZLE_NONE, pr, CU_TENSOR_MAP_FLOAT_OOB_FILL_NONE);
}

}

extern "C" void kernel_launch(void* const* d_in, const int* in_sizes, int n_in, void* d_out, int out_size) {
    (void)in_sizes; (void)n_in; (void)out_size;
    static EncodeFn fn = nullptr;
    static Scratch* scratch = nullptr;
    if (!fn) {
        cudaGetSymbolAddress((void**)&scratch, g_s);
        scratch = (Scratch*)(((uintptr_t)scratch + kScratchAlign - 1) & ~(uintptr_t)(kScratchAlign - 1));
        cudaDriverEntryPointQueryResult qr;
        cudaGetDriverEntryPoint("cuTensorMapEncodeTiled", (void**)&fn, cudaEnableDefault, &qr);
        cudaFuncSetAttribute(fused_kernel, cudaFuncAttributeMaxDynamicSharedMemorySize, SM_ALLOC);
    }
    Maps maps;
    encode(fn, &maps.we, d_in[10], 512, 3072, 256, 8, CU_TENSOR_MAP_L2_PROMOTION_L2_64B);
    encode(fn, &maps.wl, d_in[10], 512, 3072, 256, 16, CU_TENSOR_MAP_L2_PROMOTION_L2_64B);
    encode(fn, &maps.wq, d_in[3], 512, 4096, 256, 32, CU_TENSOR_MAP_L2_PROMOTION_L2_128B);
    encode(fn, &maps.v, d_in[2], 32 * 4096, 128, 128, 64, CU_TENSOR_MAP_L2_PROMOTION_NONE);
    encode(fn, &maps.wo, d_in[4], 4096, 512, 32, 256, CU_TENSOR_MAP_L2_PROMOTION_NONE);
    encode(fn, &maps.wg, d_in[6], 512, kF, 256, 16, CU_TENSOR_MAP_L2_PROMOTION_L2_64B);
    encode(fn, &maps.wu, d_in[7], 512, kF, 256, 16, CU_TENSOR_MAP_L2_PROMOTION_L2_64B);
    fused_kernel<<<kNCTA, kThreads, SM_ALLOC, cudaStreamPerThread>>>(
        (const char*)d_in[1], (const uint32_t*)d_in[0], (const uint32_t*)d_in[9], (uint32_t*)d_out, scratch,
        (const char*)d_in[8], maps);
}
```
